```python
import torch

def _softmax(x, axis=-1):
    return torch.softmax(x, dim=axis)
def _gelu(x):
    return torch.nn.functional.gelu(x, approximate="tanh")
def _silu(x):
    return torch.nn.functional.silu(x)
def _sigmoid(x):
    return torch.sigmoid(x)
def _layernorm(x, axis=-1, eps=1e-5):
    m = x.mean(dim=axis, keepdim=True)
    v = x.var(dim=axis, keepdim=True, unbiased=False)
    return (x - m) / torch.sqrt(v + eps)
def _scatter_add(tgt, idx, src, axis=0):
    return tgt.clone().index_add_(axis, idx, src)
def _segment_sum(src, seg, n):
    out = torch.zeros((n,) + src.shape[1:], dtype=src.dtype)
    return out.index_add_(0, seg, src)
def _pad(x, pw):
    flat = tuple(v for pair in reversed(pw) for v in pair)
    return torch.nn.functional.pad(x, flat)

kernel_name = 'standalone__linear_attn_block__prompt'

def setup_inputs():

    _w = (lambda a: (lambda t: t.to(torch.bfloat16) if t.is_floating_point() else t)(torch.as_tensor(a)))
    B, S, D = 1, 2048, 576
    return {
        "x": _w((lambda *s: torch.randn(*s, dtype=torch.bfloat16) * 0.05)(B, S, D)),
        "wqkv": _w((lambda *s: torch.randn(*s, dtype=torch.bfloat16) * 0.4)(D, 3 * D)),
        "wo": _w((lambda *s: torch.randn(*s, dtype=torch.bfloat16) * 0.05)(D, D)),
    }

def reference(x, wqkv, wo):
    B, S, D = x.shape
    H = 32; Dh = D // H
    qkv = (lambda x, *d: x.permute(*d))((x @ wqkv).reshape(B, S, 3, H, Dh), 2, 0, 3, 1, 4)
    q, k, v = qkv[0], qkv[1], qkv[2]
    phi = lambda t: torch.where(t > 0, t + 1, torch.exp(t)) + 1e-6
    pq, pk = phi(q), phi(k)
    kv = torch.einsum("bhsd,bhse->bhde", pk, v)
    z = torch.einsum("bhsd->bhd", pk)
    num = torch.einsum("bhqd,bhde->bhqe", pq, kv)
    den = torch.einsum("bhqd,bhd->bhq", pq, z)[..., None] + 1e-6
    o = num / den
    return (lambda x, *d: x.permute(*d))(o, 0, 2, 1, 3).reshape(B, S, D) @ wo
```

```cpp
#include <cuda_runtime.h>
#include <cuda.h>
#include <cuda_bf16.h>
#include <stdint.h>
#include <stddef.h>

#define T1 1700
#define PF 900
#define PK 566
#define HOPDELAY 330
#define HOPDELAY2 300
#define O1DELAY 70
#define POLLGATE 400
#define OPACE 110
#define PPACE 130
#define QG1 2
#define LEADPT 28
#define GAPPT 4

namespace {

constexpr int NCTA = 128;
constexpr int NTHREADS = 384;
constexpr int NF = 2;
constexpr int QS = 6;
__host__ __device__ constexpr int q_order(int i) { return i == 0 ? QS : i < 5 ? i + 1 : i + 2; }
__host__ __device__ constexpr int q_pos(int c) { return c == QS ? 0 : c < QS ? c - 1 : c - 2; }
constexpr uint32_t SM_X   = 0;
constexpr uint32_t SM_M   = 73728;
constexpr uint32_t SM_QM  = SM_M + 65536;
constexpr uint32_t SM_QR  = SM_QM + 40960;
constexpr uint32_t SM_O   = SM_M;
constexpr uint32_t SM_WR  = SM_O + 131072;
constexpr uint32_t SM_R   = SM_WR - 8192;
constexpr uint32_t SM_BKV = SM_WR + 10240;
constexpr uint32_t SM_BAR = SM_BKV + 14336;
constexpr uint32_t SM_PB  = SM_BAR + 2048;
constexpr uint32_t SM_TOTAL = SM_PB + 1024;
constexpr uint32_t SM_PK  = SM_M;
constexpr uint32_t SM_V   = SM_PK + 18432;
static_assert(SM_QR + 10240 <= SM_R && SM_TOTAL <= 232448, "smem map");
__host__ __device__ constexpr uint32_t wq_slot(int c) {
  return c == 0 ? SM_X + 65536 : c == 1 ? SM_QM : q_pos(c) < 5 ? SM_QM + q_pos(c) * 8192 : SM_M + q_pos(c) * 8192;
}
__host__ __device__ constexpr uint32_t wkv_slot(int c) { return c == 4 ? SM_QM + 3 * 8192 : SM_M + (c % 5) * 16384; }
constexpr int B_XF = 0,
              B_F = 9,
              B_RF = 18,
              B_RQ = 27,
              B_E = 32,
              B_QF = 38,
              B_QR = 47,
              B_OF = 52,
              B_XS = 83,
              B_E7 = 66,
              B_VD = 67,
              B_QD = 68,
              B_PUB = 69,
              B_DONE = 70,
              B_BKV = 71,
              B_H1 = 72,
              B_INIT = 73,
              B_RW = 74,
              B_WO = 75,
              B_OI = 76,
              B_OS = 78,
              B_O0 = 80, B_LEAD = 81, B_STG = 82,
              B_F2 = 84,
              B_NUM = 93;
constexpr uint32_t SM_EPOCH = SM_BAR + 8 * 96, SM_LOG2E = SM_EPOCH + 4, SM_DUMMY = SM_EPOCH + 8;
constexpr uint32_t bar_count(int i) {
  if (i == B_XF || i == B_RF || i == B_F || i == B_RQ || i == B_QF || i == B_RF + 1 || i == B_F2) return 0;
  if ((i >= B_F && i < B_RF) || i == B_WO) return 2;
  if ((i >= B_E && i < B_QF) || (i >= B_E7 && i <= B_DONE) || i == B_XS) return 8;
  if (i == B_BKV || i == B_H1) return 3;
  if (i >= B_OS && i < B_F2) return 4;
  return 1;
}
struct Counts { uint32_t w[12]; };

struct Maps { CUtensorMap x, wkv, wr, wq, wqr, wo, wor, out, outr; };

struct Scratch {
  uint4 o[2][32 * 8 * 576];
  uint4 flag[32 * 8];
  uint4 h1[8 * 16 * 288];
  uint4 h2[8 * 288];
  unsigned init;
};
__device__ __align__(128) Scratch g_scratch;

__device__ __forceinline__ uint32_t smem_u32(const void* p) { return (uint32_t)__cvta_generic_to_shared(p); }
__device__ __forceinline__ void mbar_init(uint32_t bar, uint32_t cnt) { asm volatile("mbarrier.init.shared::cta.b64 [%0], %1;" ::"r"(bar), "r"(cnt) : "memory"); }
__device__ __forceinline__ void mbar_expect_tx(uint32_t bar, uint32_t bytes) { asm volatile("mbarrier.arrive.expect_tx.shared::cta.b64 _, [%0], %1;" ::"r"(bar), "r"(bytes) : "memory"); }
__device__ __forceinline__ void mbar_arrive(uint32_t bar) { asm volatile("mbarrier.arrive.shared::cta.b64 _, [%0];" ::"r"(bar) : "memory"); }
__device__ __forceinline__ bool elect_one() {
  uint32_t p; asm volatile("{\n.reg .pred P;\nelect.sync _|P, 0xffffffff;\nselp.u32 %0,1,0,P;\n}" : "=r"(p)); return p;
}
__device__ __forceinline__ void mbar_wait(uint32_t bar) {
  asm volatile("{\n.reg .pred p;\nW: mbarrier.try_wait.parity.shared::cta.b64 p, [%0], 0;\n@!p bra W;\n}" ::"r"(bar) : "memory");
}
__device__ __forceinline__ void mbar_wait_bounded(uint32_t bar, unsigned t0) {
  asm volatile("{\n.reg .pred p;\n.reg .u32 c;\n"
               "W: mbarrier.try_wait.parity.shared::cta.b64 p, [%0], 0, 1000;\n@p bra D;\n"
               "mov.u32 c, %%clock;\nsub.u32 c, c, %1;\nsetp.lt.u32 p, c, 0x20000000;\n@p bra W;\ntrap;\nD:\n}" ::"r"(bar), "r"(t0) : "memory");
}
__device__ __forceinline__ void tma2d(uint32_t dst, const CUtensorMap* m, int c0, int c1, uint32_t bar) {
  asm volatile("cp.async.bulk.tensor.2d.shared::cluster.global.mbarrier::complete_tx::bytes [%0], [%1, {%3,%4}], [%2];"
               ::"r"(dst), "l"(m), "r"(bar), "r"(c0), "r"(c1) : "memory");
}
__device__ __forceinline__ void tma3d(uint32_t dst, const CUtensorMap* m, int c0, int c1, int c2, uint32_t bar) {
  asm volatile("cp.async.bulk.tensor.3d.shared::cluster.global.mbarrier::complete_tx::bytes [%0], [%1, {%3,%4,%5}], [%2];"
               ::"r"(dst), "l"(m), "r"(bar), "r"(c0), "r"(c1), "r"(c2) : "memory");
}
__device__ __forceinline__ void tma4d(uint32_t dst, const CUtensorMap* m, int c0, int c1, int c2, int c3, uint32_t bar) {
  asm volatile("cp.async.bulk.tensor.4d.shared::cluster.global.mbarrier::complete_tx::bytes [%0], [%1, {%3,%4,%5,%6}], [%2];"
               ::"r"(dst), "l"(m), "r"(bar), "r"(c0), "r"(c1), "r"(c2), "r"(c3) : "memory");
}
__device__ __forceinline__ void bulk_load(uint32_t dst, const void* src, uint32_t bytes, uint32_t bar) {
  asm volatile("cp.async.bulk.shared::cluster.global.mbarrier::complete_tx::bytes [%0], [%1], %2, [%3];" ::"r"(dst), "l"(src), "r"(bytes), "r"(bar) : "memory");
}
__device__ __forceinline__ void tma_store2d(const CUtensorMap* m, int c0, int c1, uint32_t src) {
  asm volatile("cp.async.bulk.tensor.2d.global.shared::cta.bulk_group [%0, {%2,%3}], [%1];" ::"l"(m), "r"(src), "r"(c0), "r"(c1) : "memory");
}
__device__ __forceinline__ void fence_async_smem() { asm volatile("fence.proxy.async.shared::cta;" ::: "memory"); }
__device__ __forceinline__ void fence_mbar_init() { asm volatile("fence.mbarrier_init.release.cluster;" ::: "memory"); }
__device__ __forceinline__ void bar_sync(int id, int n) { asm volatile("bar.sync %0, %1;" ::"r"(id), "r"(n) : "memory"); }
__device__ __forceinline__ void bar_arrive(int id, int n) { asm volatile("bar.arrive %0, %1;" ::"r"(id), "r"(n) : "memory"); }
__device__ __forceinline__ void wg_fence() { asm volatile("wgmma.fence.sync.aligned;" ::: "memory"); }
__device__ __forceinline__ void wg_commit() { asm volatile("wgmma.commit_group.sync.aligned;" ::: "memory"); }
template <int N> __device__ __forceinline__ void wg_wait() { asm volatile("wgmma.wait_group.sync.aligned %0;" ::"n"(N) : "memory"); }
__device__ __forceinline__ uint64_t desc64(uint32_t lo, uint32_t hi) { return (uint64_t)lo | ((uint64_t)hi << 32); }
__host__ __device__ constexpr uint32_t dlo(uint32_t addr, int lbo) { return (addr >> 4) + ((uint32_t)lbo << 12); }
constexpr uint32_t DHI_SW128 = (1024 >> 4) | (1u << 30);
__device__ __forceinline__ uint32_t pack_bf16(float lo, float hi) {
  uint32_t r; asm("cvt.rn.bf16x2.f32 %0, %1, %2;" : "=r"(r) : "f"(hi), "f"(lo)); return r;
}
constexpr float LOG2E = 1.4426950408889634f;
__device__ __forceinline__ uint32_t phi2(float t0, float t1, float log2e = LOG2E) {
  float e0, e1; uint32_t r, e;
  asm("ex2.approx.ftz.f32 %0, %1;" : "=f"(e0) : "f"(t0 * log2e));
  asm("ex2.approx.ftz.f32 %0, %1;" : "=f"(e1) : "f"(t1 * log2e));
  asm("cvt.rn.relu.bf16x2.f32 %0, %1, %2;" : "=r"(r) : "f"(t1), "f"(t0));
  asm("min.bf16x2 %0, %1, %2;" : "=r"(e) : "r"(pack_bf16(e0, e1)), "r"(0x3F803F80u));
  asm("add.rn.bf16x2 %0, %1, %2;" : "=r"(r) : "r"(r), "r"(e));
  asm("add.rn.bf16x2 %0, %1, %2;" : "=r"(r) : "r"(r), "r"(0x35863586u));
  return r;
}
__device__ __forceinline__ void stsm4(uint32_t addr, uint32_t r0, uint32_t r1, uint32_t r2, uint32_t r3) {
  asm volatile("stmatrix.sync.aligned.m8n8.x4.shared.b16 [%0], {%1,%2,%3,%4};" ::"r"(addr), "r"(r0), "r"(r1), "r"(r2), "r"(r3) : "memory");
}
__device__ __forceinline__ void stsm2(uint32_t addr, uint32_t r0, uint32_t r1) {
  asm volatile("stmatrix.sync.aligned.m8n8.x2.shared.b16 [%0], {%1,%2};" ::"r"(addr), "r"(r0), "r"(r1) : "memory");
}
__device__ __forceinline__ uint4 ldsm4(uint32_t addr) {
  uint4 v; asm volatile("ldmatrix.sync.aligned.m8n8.x4.shared.b16 {%0,%1,%2,%3}, [%4];" : "=r"(v.x), "=r"(v.y), "=r"(v.z), "=r"(v.w) : "r"(addr) : "memory"); return v;
}
__device__ __forceinline__ void sts128(uint32_t addr, uint4 v) {
  asm volatile("st.shared.v4.u32 [%0], {%1,%2,%3,%4};" ::"r"(addr), "r"(v.x), "r"(v.y), "r"(v.z), "r"(v.w) : "memory");
}
__device__ __forceinline__ void sts32(uint32_t addr, uint32_t v) { asm volatile("st.shared.u32 [%0], %1;" ::"r"(addr), "r"(v) : "memory"); }
__device__ __forceinline__ uint4 lds128(uint32_t addr) {
  uint4 v; asm volatile("ld.shared.v4.u32 {%0,%1,%2,%3}, [%4];" : "=r"(v.x), "=r"(v.y), "=r"(v.z), "=r"(v.w) : "r"(addr) : "memory"); return v;
}
__device__ __forceinline__ uint32_t lds32(uint32_t addr) {
  uint32_t v; asm volatile("ld.shared.u32 %0, [%1];" : "=r"(v) : "r"(addr) : "memory"); return v;
}
__device__ __forceinline__ uint4 ld_relaxed(const void* p) {
  uint4 v; asm volatile("ld.relaxed.gpu.global.v4.u32 {%0,%1,%2,%3}, [%4];" : "=r"(v.x), "=r"(v.y), "=r"(v.z), "=r"(v.w) : "l"(p) : "memory"); return v;
}
__device__ __forceinline__ uint32_t ld_relaxed1(const void* p) {
  uint32_t v; asm volatile("ld.relaxed.gpu.global.u32 %0, [%1];" : "=r"(v) : "l"(p) : "memory"); return v;
}
__device__ __forceinline__ void st_relaxed(void* p, uint4 v) {
  asm volatile("st.relaxed.gpu.global.v4.u32 [%0], {%1,%2,%3,%4};" ::"l"(p), "r"(v.x), "r"(v.y), "r"(v.z), "r"(v.w) : "memory");
}
__device__ __forceinline__ void st_relaxed1(void* p, uint32_t a) { asm volatile("st.relaxed.gpu.global.u32 [%0], %1;" ::"l"(p), "r"(a) : "memory"); }
__device__ __forceinline__ unsigned ld_acquire(const unsigned* p) {
  unsigned v; asm volatile("ld.acquire.gpu.global.u32 %0, [%1];" : "=r"(v) : "l"(p) : "memory"); return v;
}
__device__ __forceinline__ unsigned clk() { unsigned c; asm volatile("mov.u32 %0, %%clock;" : "=r"(c)); return c; }
__device__ __forceinline__ void wait_until(unsigned t0, unsigned n) { while (clk() - t0 < n) {} }
__device__ __forceinline__ void spin(unsigned n) { wait_until(clk(), n); }
__host__ __device__ constexpr unsigned t_issue(int c) { return c <= NF ? T1 + (c - 1) * PF : T1 + (NF - 1) * PF + (c - NF) * PK; }
template <int N> __device__ __forceinline__ void reg_fence(float (&d)[N]) {
#pragma unroll
  for (int i = 0; i < N; i++) asm volatile("" : "+f"(d[i])::"memory");
}

__device__ __forceinline__ uint32_t sel(int c, uint32_t a, uint32_t b) {
  uint32_t r; asm("{\n.reg .pred p;\nsetp.ne.b32 p, %3, 0;\nselp.b32 %0, %1, %2, p;\n}" : "=r"(r) : "r"(a), "r"(b), "r"(c)); return r;
}
__device__ __forceinline__ void pin(uint32_t& a) { asm volatile("" : "+r"(a)::"memory"); }
__device__ __forceinline__ void pin(uint4& a) { asm volatile("" : "+r"(a.x), "+r"(a.y), "+r"(a.z), "+r"(a.w)::"memory"); }

__device__ __forceinline__ void wgmma_rs_n72(float (&d)[36], uint32_t a0, uint32_t a1, uint32_t a2, uint32_t a3, uint64_t db, int sc) {
  asm volatile("{\n.reg .pred p;\nsetp.ne.b32 p, %41, 0;\n"
    "wgmma.mma_async.sync.aligned.m64n72k16.f32.bf16.bf16 {%0,%1,%2,%3,%4,%5,%6,%7,%8,%9,%10,%11,%12,%13,%14,%15,%16,%17,%18,%19,%20,%21,%22,%23,%24,%25,%26,%27,%28,%29,%30,%31,%32,%33,%34,%35}, {%36,%37,%38,%39}, %40, p, 1, 1, 1;\n}\n"
    : "+f"(d[0]),"+f"(d[1]),"+f"(d[2]),"+f"(d[3]),"+f"(d[4]),"+f"(d[5]),"+f"(d[6]),"+f"(d[7]),"+f"(d[8]),"+f"(d[9]),"+f"(d[10]),"+f"(d[11]),"+f"(d[12]),"+f"(d[13]),"+f"(d[14]),"+f"(d[15]),"+f"(d[16]),"+f"(d[17]),"+f"(d[18]),"+f"(d[19]),"+f"(d[20]),"+f"(d[21]),"+f"(d[22]),"+f"(d[23]),"+f"(d[24]),"+f"(d[25]),"+f"(d[26]),"+f"(d[27]),"+f"(d[28]),"+f"(d[29]),"+f"(d[30]),"+f"(d[31]),"+f"(d[32]),"+f"(d[33]),"+f"(d[34]),"+f"(d[35])
    : "r"(a0),"r"(a1),"r"(a2),"r"(a3),"l"(db),"r"(sc));
}
__device__ __forceinline__ void wgmma_ss_n72(float (&d)[36], uint64_t da, uint64_t db, int sc) {
  asm volatile("{\n.reg .pred p;\nsetp.ne.b32 p, %38, 0;\n"
    "wgmma.mma_async.sync.aligned.m64n72k16.f32.bf16.bf16 {%0,%1,%2,%3,%4,%5,%6,%7,%8,%9,%10,%11,%12,%13,%14,%15,%16,%17,%18,%19,%20,%21,%22,%23,%24,%25,%26,%27,%28,%29,%30,%31,%32,%33,%34,%35}, %36, %37, p, 1, 1, 0, 1;\n}\n"
    : "+f"(d[0]),"+f"(d[1]),"+f"(d[2]),"+f"(d[3]),"+f"(d[4]),"+f"(d[5]),"+f"(d[6]),"+f"(d[7]),"+f"(d[8]),"+f"(d[9]),"+f"(d[10]),"+f"(d[11]),"+f"(d[12]),"+f"(d[13]),"+f"(d[14]),"+f"(d[15]),"+f"(d[16]),"+f"(d[17]),"+f"(d[18]),"+f"(d[19]),"+f"(d[20]),"+f"(d[21]),"+f"(d[22]),"+f"(d[23]),"+f"(d[24]),"+f"(d[25]),"+f"(d[26]),"+f"(d[27]),"+f"(d[28]),"+f"(d[29]),"+f"(d[30]),"+f"(d[31]),"+f"(d[32]),"+f"(d[33]),"+f"(d[34]),"+f"(d[35])
    : "l"(da),"l"(db),"r"(sc));
}
__device__ __forceinline__ void wgmma_tt_n48(float (&d)[24], uint64_t da, uint64_t db, int sc) {
  asm volatile("{\n.reg .pred p;\nsetp.ne.b32 p, %26, 0;\n"
    "wgmma.mma_async.sync.aligned.m64n48k16.f32.bf16.bf16 {%0,%1,%2,%3,%4,%5,%6,%7,%8,%9,%10,%11,%12,%13,%14,%15,%16,%17,%18,%19,%20,%21,%22,%23}, %24, %25, p, 1, 1, 1, 1;\n}\n"
    : "+f"(d[0]),"+f"(d[1]),"+f"(d[2]),"+f"(d[3]),"+f"(d[4]),"+f"(d[5]),"+f"(d[6]),"+f"(d[7]),"+f"(d[8]),"+f"(d[9]),"+f"(d[10]),"+f"(d[11]),"+f"(d[12]),"+f"(d[13]),"+f"(d[14]),"+f"(d[15]),"+f"(d[16]),"+f"(d[17]),"+f"(d[18]),"+f"(d[19]),"+f"(d[20]),"+f"(d[21]),"+f"(d[22]),"+f"(d[23])
    : "l"(da),"l"(db),"r"(sc));
}
__device__ __forceinline__ void wgmma_rs_n48(float (&d)[24], uint32_t a0, uint32_t a1, uint32_t a2, uint32_t a3, uint64_t db, int sc) {
  asm volatile("{\n.reg .pred p;\nsetp.ne.b32 p, %29, 0;\n"
    "wgmma.mma_async.sync.aligned.m64n48k16.f32.bf16.bf16 {%0,%1,%2,%3,%4,%5,%6,%7,%8,%9,%10,%11,%12,%13,%14,%15,%16,%17,%18,%19,%20,%21,%22,%23}, {%24,%25,%26,%27}, %28, p, 1, 1, 1;\n}\n"
    : "+f"(d[0]),"+f"(d[1]),"+f"(d[2]),"+f"(d[3]),"+f"(d[4]),"+f"(d[5]),"+f"(d[6]),"+f"(d[7]),"+f"(d[8]),"+f"(d[9]),"+f"(d[10]),"+f"(d[11]),"+f"(d[12]),"+f"(d[13]),"+f"(d[14]),"+f"(d[15]),"+f"(d[16]),"+f"(d[17]),"+f"(d[18]),"+f"(d[19]),"+f"(d[20]),"+f"(d[21]),"+f"(d[22]),"+f"(d[23])
    : "r"(a0),"r"(a1),"r"(a2),"r"(a3),"l"(db),"r"(sc));
}
__device__ __forceinline__ void wgmma_rs_n40(float (&d)[20], uint32_t a0, uint32_t a1, uint32_t a2, uint32_t a3, uint64_t db, int sc) {
  asm volatile("{\n.reg .pred p;\nsetp.ne.b32 p, %25, 0;\n"
    "wgmma.mma_async.sync.aligned.m64n40k16.f32.bf16.bf16 {%0,%1,%2,%3,%4,%5,%6,%7,%8,%9,%10,%11,%12,%13,%14,%15,%16,%17,%18,%19}, {%20,%21,%22,%23}, %24, p, 1, 1, 1;\n}\n"
    : "+f"(d[0]),"+f"(d[1]),"+f"(d[2]),"+f"(d[3]),"+f"(d[4]),"+f"(d[5]),"+f"(d[6]),"+f"(d[7]),"+f"(d[8]),"+f"(d[9]),"+f"(d[10]),"+f"(d[11]),"+f"(d[12]),"+f"(d[13]),"+f"(d[14]),"+f"(d[15]),"+f"(d[16]),"+f"(d[17]),"+f"(d[18]),"+f"(d[19])
    : "r"(a0),"r"(a1),"r"(a2),"r"(a3),"l"(db),"r"(sc));
}

__device__ __forceinline__ void mma72(float (&d)[36], const uint4& a, uint32_t blo, int sc) { wgmma_rs_n72(d, a.x, a.y, a.z, a.w, desc64(blo, DHI_SW128), sc); }

constexpr uint32_t POISON = 0xFFFFFFFFu;
__device__ __forceinline__ uint32_t umax4(const uint4& v) { return max(max(v.x, v.y), max(v.z, v.w)); }

__device__ __forceinline__ float rcp(float x) { float r; asm("rcp.approx.ftz.f32 %0, %1;" : "=f"(r) : "f"(x)); return r; }
template <int N0, int N1, int NA> __device__ __forceinline__ void normalise(const float (&o)[NA], const float (&r)[2][4], uint32_t (&f)[18], int t8,
                                                                            uint32_t* ow, uint32_t* ow8) {
#pragma unroll
  for (int n = N0; n < N1; n++) {
    const int h0 = (8 * n) / 18, h1 = (8 * n + 14) / 18;
#pragma unroll
    for (int h = 0; h < 2; h++) {
      const float s = h0 == h1 ? r[h][h0] : t8 >= 18 * h1 - 8 * n ? r[h][h1 & 3] : r[h][h0];
      const int i = NA - 4 * (N1 - n) + 2 * h;
      f[2 * n + h] = pack_bf16(o[i] * s, o[i + 1] * s);
      st_relaxed1((n < 8 ? ow + n * 256 : ow8) + h * 32, f[2 * n + h]);
    }
  }
}

__device__ __forceinline__ void swizzle_job(uint32_t base, int lane) {
  uint4 v[4];
#pragma unroll
  for (int h = 0; h < 4; h++) v[h] = lds128(base + h * 512 + lane * 16);
  __syncwarp();
#pragma unroll
  for (int h = 0; h < 4; h++) sts128(base + h * 512 + (lane >> 3) * 128 + (((lane & 7) ^ ((h & 1) * 4 + (lane >> 3))) << 4), v[h]);
  fence_async_smem(); __syncwarp();
}

__global__ void __launch_bounds__(NTHREADS, 1)
linattn_kernel(const __nv_bfloat16* __restrict__ wo, Scratch* __restrict__ scr, const __grid_constant__ Counts counts,
               const __grid_constant__ Maps maps) {
  extern __shared__ __align__(1024) unsigned char smem_raw[];
  const unsigned t_start = clk();
  uint4* const g_h1 = scr->h1; uint4* const g_h2 = scr->h2;
  constexpr uint32_t sb = 1024;
  constexpr uint32_t bar = sb + SM_BAR;
  const int tid = threadIdx.x, lane = tid & 31;
  const int b = blockIdx.x;
  const int ti = ((b >> 2) ^ -(b >> 6)) & 15, tj = ((b >> 6) << 2) | (b & 3);
  const int odd = tj & 1;
  const int colm = 72 * tj + (odd ? 8 : 0);
  const int colr = 72 * tj + (odd ? 0 : 64);

#define LOAD_X(c)  do { mbar_expect_tx(bar + 8 * (B_XF + (c)), 16384); tma2d(sb + SM_X + ((c) & 3) * 16384, &maps.x, (c) * 64, ti * 128, bar + 8 * (B_XF + (c))); } while (0)
#define LOAD_R(c)  do { mbar_expect_tx(bar + 8 * (B_RF + (c)), 2048); tma4d(sb + SM_R + (8 - (c)) * 2048, &maps.wr, colr, 1, (c) * 4, 0, bar + 8 * (B_RF + (c))); } while (0)
#define LOAD_QR(a) do { mbar_expect_tx(bar + 8 * (B_RQ + (a)), 2048); tma4d(sb + SM_QR + (a) * 2048, &maps.wqr, colr, 0, (a) * 8, 0, bar + 8 * (B_RQ + (a))); } while (0)
#define LOAD_W(c)  do { mbar_expect_tx(bar + 8 * (B_F + (c)), 8192); tma3d(sb + wkv_slot(c), &maps.wkv, colm, (c) * 64, 1, bar + 8 * (B_F + (c))); \
                        mbar_expect_tx(bar + 8 * (B_F2 + (c)), 8192); tma3d(sb + wkv_slot(c) + 8192, &maps.wkv, colm, (c) * 64 + 32, 1, bar + 8 * (B_F2 + (c))); } while (0)
#define LOAD_Q(c)  do { mbar_expect_tx(bar + 8 * (B_QF + (c)), 8192); tma2d(sb + wq_slot(c), &maps.wq, colm, (c) * 64, bar + 8 * (B_QF + (c))); } while (0)
  if (tid >= 352) {
    if (elect_one()) {
      mbar_init(bar + 8 * B_XF, 1); mbar_init(bar + 8 * B_RF, 1); mbar_init(bar + 8 * B_F, 2);
      mbar_init(bar + 8 * B_RQ, 1); mbar_init(bar + 8 * B_QF, 1); mbar_init(bar + 8 * (B_RF + 1), 1); mbar_init(bar + 8 * B_F2, 1);
      fence_mbar_init();
      LOAD_R(0); LOAD_X(0); LOAD_W(0); LOAD_QR(0); LOAD_Q(0); LOAD_R(1);
    }
    __syncwarp();
  }
  const int warp = __shfl_sync(0xffffffffu, tid >> 5, 0);
  if (warp < 10) {
    const uint32_t o1 = offsetof(Scratch, h1) + (tj * 16 * 288 + ti * 18 + tid + ((tid * 3641) >> 16) * 270) * 16;
    const uint32_t o2 = offsetof(Scratch, h2) + (tj * 288 + ti * 18 + lane) * 16;
    const uint32_t o3 = offsetof(Scratch, flag) + (ti * 2 + (lane & 1)) * 128 + tj * 16;
    st_relaxed((char*)scr + (warp < 9 ? o1 : sel(lane < 18, o2, o3)), make_uint4(POISON, POISON, POISON, POISON));
  }
  if (warp < 11) {
    if (elect_one()) {
      const uint32_t cw = counts.w[warp];
#pragma unroll
      for (int i = 0; i < 8; i++) if ((cw >> (4 * i)) & 15) mbar_init(bar + 64 * warp + 8 * i, (cw >> (4 * i)) & 15);
      if (warp + 88 < B_NUM) mbar_init(bar + 8 * (88 + warp), 1);
      fence_mbar_init();
    }
    __syncwarp();
  }

  if (warp < 8) {
    asm volatile("setmaxnreg.inc.sync.aligned.u32 232;");
    const int m = warp >> 2, w = warp & 3;
    const int g = lane >> 2, t = lane & 3;
    bar_sync(0, NTHREADS);
    const uint32_t xa = sb + SM_X + (warp * 16 + (lane & 15)) * 128 + (((lane >> 4) ^ (lane & 7)) << 4);
    uint4 fr[9][4];
    float k[36], v[36], q[36];
#define LDH(c, h) do { _Pragma("unroll") for (int kk = 2 * (h); kk < 2 * (h) + 2; kk++) fr[c][kk] = ldsm4((xa ^ (kk << 5)) + ((c) & 3) * 16384); } while (0)
#define WOFF(c, kk, s) (wkv_slot(c) + ((kk) >> 1) * 8192 + (s) * 4096 + ((kk) & 1) * 2048)
#define WBLO(c, kk, s) dlo(sb + WOFF(c, kk, s), SM_R + (8 - (c)) * 2048 + (kk) * 32 + (s) * 16 - WOFF(c, kk, s))
#define KSTEP(c, kk) mma72(k, fr[c][kk], WBLO(c, kk, 0), ((c) | (kk)) != 0)
#define VSTEP(c, kk) mma72(v, fr[c][kk], WBLO(c, kk, 1), ((c) | (kk)) != 0)
#define QBLO(c, kk) dlo(sb + wq_slot(c) + (kk) * 2048, SM_QR + ((c) >> 1) * 2048 + (((c) & 1) * 4 + (kk)) * 16 - wq_slot(c) - (kk) * 2048)
#define QSTEP(c, kk) do { if ((c) == QS) wgmma_ss_n72(q, desc64(dlo(sb + SM_X + ((c) & 3) * 16384 + (kk) * 32, 16) + m * 512, DHI_SW128), desc64(QBLO(c, kk), DHI_SW128), 1); \
                          else mma72(q, fr[c][kk], QBLO(c, kk), ((c) | (kk)) != 0); } while (0)
#define QWAIT(c) do { if ((c) >= NF || !((c) & 1)) mbar_wait(bar + 8 * (B_QR + ((c) >> 1))); mbar_wait(bar + 8 * (B_QF + (c))); } while (0)
#define QMMA(c) do { wg_fence(); _Pragma("unroll") for (int kk = 0; kk < 4; kk++) QSTEP(c, kk); wg_commit(); } while (0)
#define QCHUNK(c) do { QWAIT(c); QMMA(c); } while (0)
    mbar_wait(bar + 8 * B_XF);
    LDH(0, 0); LDH(0, 1);
#pragma unroll
    for (int c = 0; c < 8; c++) {
      mbar_wait(bar + 8 * (B_F + c));
      if (c > 0) LDH(c, 1);
      wg_fence();
#pragma unroll
      for (int kk = 0; kk < 2; kk++) { KSTEP(c, kk); VSTEP(c, kk); }
      wg_commit();
      wg_wait<1>();
      pin(fr[c][2]); pin(fr[c][3]);
      mbar_wait(bar + 8 * (B_F2 + c));
      if (c >= NF) { mbar_wait(bar + 8 * (B_XF + c + 1)); LDH(c + 1, 0); }
      wg_fence();
      if (c < 6 && lane == 0) mbar_arrive(bar + 8 * (B_E + c));
#pragma unroll
      for (int kk = 2; kk < 4; kk++) { KSTEP(c, kk); VSTEP(c, kk); }
      if (c == 0) { QCHUNK(c); mbar_wait(bar + 8 * (B_XF + c + 1)); LDH(c + 1, 0); }
      else if (c < NF) { QWAIT(c); mbar_wait(bar + 8 * (B_XF + c + 1)); LDH(c + 1, 0); QMMA(c); }
      else wg_commit();
    }
    mbar_wait(bar + 8 * (B_F + 8));
    LDH(8, 1);
    wg_fence();
    KSTEP(8, 0); KSTEP(8, 1);
    pin(fr[8][2]); pin(fr[8][3]);
    mbar_wait(bar + 8 * (B_F2 + 8));
    wg_fence();
    KSTEP(8, 2); KSTEP(8, 3);
    wg_commit();
    wg_wait<1>();
    if (lane == 0) mbar_arrive(bar + 8 * B_E7);
    wg_fence();
#pragma unroll
    for (int kk = 0; kk < 4; kk++) VSTEP(8, kk);
    wg_commit();
    mbar_wait(bar + 8 * B_INIT);
    mbar_wait(bar + 8 * B_E7);
    wg_wait<1>();
    reg_fence(k);
    const uint32_t pa = sb + SM_PK + (warp * 16 + (lane & 15)) * 16 + ((lane >> 4) + odd) * 2048;
    const uint32_t pr = sb + SM_PK + (warp * 16 + (lane & 15)) * 16 + (odd ? 0 : 8 * 2048);
#define PKSTAGE(n, l) stsm4(pa + (n) * 4096, phi2(k[8 * (n)], k[8 * (n) + 1], l), phi2(k[8 * (n) + 2], k[8 * (n) + 3], l), \
                            phi2(k[8 * (n) + 4], k[8 * (n) + 5], l), phi2(k[8 * (n) + 6], k[8 * (n) + 7], l))
    {
      sts128(sb + SM_V + m * 10 * 2048 + (tid & 127) * 16, make_uint4(0x3F803F80u, 0x3F803F80u, 0x3F803F80u, 0x3F803F80u));
      PKSTAGE(0, LOG2E);
      const float la = __uint_as_float(lds32(sb + SM_LOG2E));
      stsm2(pr, phi2(k[32], k[33]), phi2(k[34], k[35]));
      PKSTAGE(1, LOG2E);
      const float lb = __uint_as_float(lds32(sb + SM_LOG2E));
      wg_wait<0>();
      reg_fence(v);
      if (lane == 0) mbar_arrive(bar + 8 * B_VD);
#pragma unroll
      for (int n = 0; n < 4; n++)
        stsm4(pa + (SM_V - SM_PK) + 2048 + n * 4096, pack_bf16(v[8 * n], v[8 * n + 1]), pack_bf16(v[8 * n + 2], v[8 * n + 3]),
              pack_bf16(v[8 * n + 4], v[8 * n + 5]), pack_bf16(v[8 * n + 6], v[8 * n + 7]));
      stsm2(pr + (SM_V - SM_PK) + 2048, pack_bf16(v[32], v[33]), pack_bf16(v[34], v[35]));
      PKSTAGE(2, la);
      PKSTAGE(3, lb);
    }
    fence_async_smem();
    bar_sync(1, 256);
    {
      float c[24];
      wg_fence();
#pragma unroll
      for (int s = 0; s < 8; s++)
        wgmma_tt_n48(c, desc64(dlo(sb + SM_PK + s * 256, 128) + m * 128, 128), desc64(dlo(sb + SM_V + s * 256, 128) + m * 640, 128), s != 0);
      wg_commit();
      const int d0 = 16 * w + g + 8 * m;
      uint4* dst[2];
#pragma unroll
      for (int h = 0; h < 2; h++) { const int V = (d0 + 8 * h) * 4 + t; dst[h] = g_h1 + tj * 16 * 288 + ti * 18 + V + ((V * 3641) >> 16) * 270; }
      wg_wait<0>();
      reg_fence(c);
#pragma unroll
      for (int h = 0; h < 2; h++) {
        const int dl = d0 + 8 * h - 36 * m;
        uint32_t p[6];
#pragma unroll
        for (int u = 0; u < 6; u++) p[u] = pack_bf16(c[4 * u + 2 * h], c[4 * u + 2 * h + 1]);
        const uint32_t z = sel(m, p[5], p[0]);
#pragma unroll
        for (int u = 0; u < 5; u++) p[u] = sel(m, p[u], p[u + 1]);
        const uint4 val = make_uint4(sel(dl >= 18, p[2], p[0]), sel(dl >= 18, p[3], p[1]), sel(dl >= 18, p[4], p[2]), z);
        if ((unsigned)dl < 36u) st_relaxed(dst[h], val);
      }
      __syncwarp();
      if (lane == 0) mbar_arrive(bar + 8 * B_PUB);
    }
#pragma unroll
    for (int i = 0; i < 9 - NF; i++) {
      if (i == QG1 && m == 1) mbar_wait(bar + 8 * B_H1);
      QCHUNK(q_order(i));
      if (i == 1) { wg_wait<1>(); if (lane == 0) mbar_arrive(bar + 8 * B_XS); }
    }
    wg_wait<0>();
    reg_fence(q);
    if (lane == 0) mbar_arrive(bar + 8 * B_QD);
    uint32_t f[18], epoch;
    {
      uint32_t pq[18];
#pragma unroll
      for (int n = 0; n < 18; n++) { pq[n] = phi2(q[2 * n], q[2 * n + 1]); pin(pq[n]); }
      uint32_t z0 = 0, z1 = 0; pin(z0); pin(z1);
      epoch = lds32(sb + SM_EPOCH);
      const uint32_t oo = (epoch & 1) * (uint32_t)sizeof(scr->o[0]) + ((ti * 2 + m) * 8 + tj) * 9216 + w * 256 + lane * 4;
      uint32_t* ow = (uint32_t*)((char*)scr + __shfl_sync(0xffffffffu, oo + odd * 1024, lane));
      uint32_t* ow8 = (uint32_t*)((char*)scr + __shfl_sync(0xffffffffu, oo + (odd ? 0 : 8192), lane));
      uint32_t* fw = (uint32_t*)((char*)scr + __shfl_sync(0xffffffffu, (uint32_t)offsetof(Scratch, flag) + ((ti * 2 + m) * 8 + tj) * 16 + w * 4, lane));
      const int t8 = 8 * odd + 2 * t;
      if (m == 1) { mbar_wait(bar + 8 * B_O0); spin(O1DELAY); __syncwarp(); }
      if (m == 0) bar_sync(4, 224);
      float o1[24], o2[20], r[2][4];
      wg_fence();
#pragma unroll
      for (int s = 0; s < 4; s++) wgmma_rs_n48(o1, pq[4 * s], pq[4 * s + 1], pq[4 * s + 2], pq[4 * s + 3], desc64(dlo(sb + SM_BKV + s * 256, 128), 80), s != 0);
      wgmma_rs_n48(o1, pq[16], pq[17], z0, z1, desc64(dlo(sb + SM_BKV + 4 * 256, 128), 80), 1);
      wg_commit();
#pragma unroll
      for (int s = 0; s < 4; s++) wgmma_rs_n40(o2, pq[4 * s], pq[4 * s + 1], pq[4 * s + 2], pq[4 * s + 3], desc64(dlo(sb + SM_BKV + 6 * 1280 + s * 256, 128), 80), s != 0);
      wgmma_rs_n40(o2, pq[16], pq[17], z0, z1, desc64(dlo(sb + SM_BKV + 6 * 1280 + 4 * 256, 128), 80), 1);
      wg_commit();
      wg_wait<1>();
      reg_fence(o1);
      if (m == 0 && lane == 0) mbar_arrive(bar + 8 * B_O0);
#pragma unroll
      for (int h = 0; h < 2; h++) {
        r[h][0] = rcp(o1[2 * h] + 1e-6f); r[h][1] = rcp(o1[1 + 2 * h] + 1e-6f);
        r[h][2] = rcp(o1[4 + 2 * h] + 1e-6f); r[h][3] = rcp(o1[5 + 2 * h] + 1e-6f);
      }
      normalise<0, 4>(o1, r, f, t8, ow, ow8);
      mbar_wait(bar + 8 * B_INIT);
      wg_wait<0>();
      reg_fence(o2);
      normalise<4, 9>(o2, r, f, t8, ow, ow8);
      if (lane == 0 && epoch != 0) st_relaxed1(fw, 0u);
      if (epoch == 0) { __syncwarp(); asm volatile("fence.acq_rel.gpu;" ::: "memory"); if (lane == 0) st_relaxed1(fw, 0u); }
      if (lane == 0) mbar_arrive(bar + 8 * (B_OS + m));
    }
    float acc[36];
    const int oc0 = __shfl_sync(0xffffffffu, tj * 64, 0), oc1 = __shfl_sync(0xffffffffu, 512 + tj * 8, 0);
    const int orow = __shfl_sync(0xffffffffu, ti * 128 + warp * 16, 0);
#define OBLO(ks) (dlo(sb + SM_X, SM_WR - SM_X) + (ks) * dlo(2048, 16 - 2048) + ((ks) >> 3) * dlo(0, 2048 - 128))
    {
      const int u0 = 9 * (tj >> 1) + 5 * odd;
      mbar_wait(bar + 8 * B_QD);
      const uint32_t ha = sb + SM_O + m * 65536 + tj * 9216 + w * 256 + lane * 4;
      sts32(ha, f[16]); sts32(ha + 128, f[17]);
      fence_async_smem();
#pragma unroll
      for (int n = 0; n < 16; n++) pin(f[n]);
      mbar_wait(bar + 8 * B_WO);
      wg_fence();
#pragma unroll
      for (int i = 0; i < 4; i++) wgmma_rs_n72(acc, f[4 * i], f[4 * i + 1], f[4 * i + 2], f[4 * i + 3], desc64(OBLO(u0 + i), DHI_SW128), i != 0);
      bar_sync(2 + m, 128);
      if (m == 1) mbar_wait(bar + 8 * B_LEAD);
      const uint32_t alo = dlo(sb + SM_O, 1024) + m * 4096;
#pragma unroll
      for (int u = 0; u < 32; u++) {
        if (u == LEADPT && m == 0 && lane == 0) mbar_arrive(bar + 8 * B_LEAD);
        if (u == GAPPT && m == 1) mbar_wait(bar + 8 * B_STG);
        if ((2 * u + 1) / 9 < 7 && (u == 0 || (2 * u + 1) / 9 != (2 * u - 1) / 9)) {
          mbar_wait(bar + 8 * (B_OF + m * 7 + (2 * u + 1) / 9));
          wg_fence();
        } else if (u == GAPPT || u == LEADPT) wg_fence();
        wgmma_ss_n72(acc, desc64(alo + u * 128, 8), desc64(u >= u0 ? OBLO(u + 4) : OBLO(u), DHI_SW128), 1);
      }
      wg_commit();
    }
    {
      const uint32_t so = sb + SM_O + m * 65536 + w * 2048, oa = so + (lane & 15) * 128;
      const uint32_t sr = sb + SM_O + m * 65536 + 8192 + w * 256;
      wg_wait<0>();
      reg_fence(acc);
      if (m == 0 && lane == 0) mbar_arrive(bar + 8 * B_STG);
#define STORE_OUT() do {                                                                         \
      _Pragma("unroll") for (int n = 0; n < 4; n++)                                              \
        stsm4(oa + (((2 * n + (lane >> 4)) ^ (lane & 7)) << 4),                                  \
              pack_bf16(acc[8 * n], acc[8 * n + 1]), pack_bf16(acc[8 * n + 2], acc[8 * n + 3]),  \
              pack_bf16(acc[8 * n + 4], acc[8 * n + 5]), pack_bf16(acc[8 * n + 6], acc[8 * n + 7])); \
      stsm2(sr + (lane & 15) * 16, pack_bf16(acc[32], acc[33]), pack_bf16(acc[34], acc[35]));    \
      fence_async_smem(); __syncwarp();                                                          \
      if (elect_one()) {                                                                         \
        tma_store2d(&maps.out, oc0, orow, so);                                                   \
        tma_store2d(&maps.outr, oc1, orow, sr);                                                  \
        asm volatile("cp.async.bulk.commit_group;" ::: "memory");                                \
      } } while (0)
      STORE_OUT();
      uint32_t redo;
      asm volatile("{\n.reg .pred p, q;\nsetp.nan.f32 p, %1, %2;\nbar.red.or.pred q, %3, 128, p;\nselp.b32 %0, 1, 0, q;\n}"
                   : "=r"(redo) : "f"(acc[0]), "f"(acc[2]), "r"(2 + m) : "memory");
      if (__builtin_expect(redo, 0)) {
        const uint32_t* or_ = (const uint32_t*)(scr->o[epoch & 1] + (ti * 2 + m) * 8 * 576) + w * 64 + lane;
#pragma unroll 1
        for (int ks = 0; ks < 36; ks++) {
          uint4 a;
          do {
            a.x = ld_relaxed1(or_ + ks * 512); a.y = ld_relaxed1(or_ + ks * 512 + 32);
            a.z = ld_relaxed1(or_ + ks * 512 + 256); a.w = ld_relaxed1(or_ + ks * 512 + 288);
          } while (__any_sync(0xffffffffu, umax4(a) == POISON));
          pin(a);
          wg_fence();
          mma72(acc, a, OBLO(ks), ks != 0);
          wg_commit();
          wg_wait<0>();
        }
        reg_fence(acc);
        asm volatile("cp.async.bulk.wait_group 0;" ::: "memory");
        asm volatile("fence.proxy.async;" ::: "memory");
        __syncwarp();
        STORE_OUT();
      }
      if (lane == 0) mbar_arrive(bar + 8 * B_DONE);
      asm volatile("cp.async.bulk.wait_group.read 0;" ::: "memory");
    }
  } else {
    asm volatile("setmaxnreg.dec.sync.aligned.u32 40;");
    if (warp < 11) {
      if (warp == 10) {
        if (smem_u32(smem_raw) != sb) __trap();
        bar_sync(0, NTHREADS);
#pragma unroll 4
        for (int i = 0; i < 28; i++) sts128(sb + SM_BKV + i * 512 + lane * 16, make_uint4(0, 0, 0, 0));
        sts32(sb + SM_LOG2E, __float_as_uint(LOG2E));
        sts128(sb + SM_PB + lane * 16, make_uint4(POISON, POISON, POISON, POISON));
        sts128(sb + SM_PB + 512 + lane * 16, make_uint4(POISON, POISON, POISON, POISON));
        fence_async_smem(); __syncwarp();
        if (lane == 0) {
          unsigned old;
          asm volatile("atom.release.gpu.global.add.u32 %0, [%1], 1;" : "=r"(old) : "l"(&scr->init) : "memory");
          const unsigned target = ((old >> 7) + 1u) << 7;
          mbar_wait(bar + 8 * (B_E + 4));
          while ((int)(ld_acquire(&scr->init) - target) < 0) {}
          sts32(sb + SM_EPOCH, old >> 7);
          mbar_arrive(bar + 8 * B_INIT);
        }
        __syncwarp();
      } else {
        bar_sync(0, NTHREADS);
        const int nj = warp == 8 ? 9 : 5;
#pragma unroll 1
        for (int job = 0; job < nj; job++) {
          mbar_wait(bar + 8 * ((warp == 8 ? B_RF : B_RQ) + job));
          swizzle_job(sb + (warp == 8 ? SM_R + (8 - job) * 2048 : SM_QR + job * 2048), lane);
          if (lane == 0) mbar_arrive(bar + 8 * ((warp == 8 ? B_F : B_QR) + job));
        }
      }
      const int ht = tid - 256, hw = (warp - 8) * 24 + (lane < 24 ? lane : lane - 8);
      uint32_t* h2w = (uint32_t*)(g_h2 + tj * 288 + ti * 18) + hw;
      mbar_wait(bar + 8 * B_INIT);
      mbar_wait(bar + 8 * B_PUB);
      spin(HOPDELAY);
#define LO(u) __uint_as_float((u) << 16)
#define HI(u) __uint_as_float((u) & 0xFFFF0000u)
      {
        float b0, b1;
        while (true) {
          const uint32_t* h1 = (const uint32_t*)(g_h1 + (tj * 16 + ti) * 288) + hw;
          uint4 p[4];
#pragma unroll
          for (int i = 0; i < 4; i++) p[i] = make_uint4(ld_relaxed1(h1 + 288 * i), ld_relaxed1(h1 + 288 * i + 72), ld_relaxed1(h1 + 288 * i + 144), ld_relaxed1(h1 + 288 * i + 216));
#define SUM4(F, c) ((F(p[0].c) + F(p[1].c)) + (F(p[2].c) + F(p[3].c)))
          b0 = (SUM4(LO, x) + SUM4(LO, y)) + (SUM4(LO, z) + SUM4(LO, w));
          b1 = (SUM4(HI, x) + SUM4(HI, y)) + (SUM4(HI, z) + SUM4(HI, w));
          if (!__any_sync(0xffffffffu, max(max(umax4(p[0]), umax4(p[1])), max(umax4(p[2]), umax4(p[3]))) == POISON)) break;
        }
        st_relaxed1(h2w, pack_bf16(b0, b1));
      }
      const unsigned t_hop = clk();
      if (lane == 0) mbar_arrive(bar + 8 * B_H1);
      int hq = ht;
      asm volatile("" : "+r"(hq) :: "memory");
      const uint4* h2 = g_h2 + tj * 288 + hq;
      uint32_t fa0[3], fa1[3], fa2[3], faz[3];
#pragma unroll
      for (int r = 0; r < 3; r++) {
        const int d = (hq >> 2) + 24 * r, t = hq & 3, head = (d * 57) >> 10;
        uint32_t rowa = sb + SM_BKV + (d - 8 * odd) * 16 + t * 4;
        if (r == 0) rowa += sel(d < 8 * odd, 72 * 16, 0);
        fa1[r] = rowa + (2 * head + 3 - odd) * 1280;
        fa0[r] = fa1[r] - 1280;
        if (r == 0) fa0[r] += sel(head < odd, 9 * 1280, 0);
        fa0[r] = sel(t < head, sb + SM_DUMMY, fa0[r]);
        fa2[r] = sel(t > head, sb + SM_DUMMY, fa1[r] + 1280);
        faz[r] = rowa + (head >> 1) * 1280 + (head & 1) * 2;
        pin(fa0[r]); pin(fa1[r]); pin(fa2[r]); pin(faz[r]);
      }
      uint4 e[3];
      wait_until(t_hop, HOPDELAY2);
      do {
#pragma unroll
        for (int r = 0; r < 3; r++) e[r] = ld_relaxed(h2 + 96 * r);
      } while (__any_sync(0xffffffffu, max(max(umax4(e[0]), umax4(e[1])), umax4(e[2])) == POISON));
#pragma unroll
      for (int r = 0; r < 3; r++) {
        sts32(fa0[r], e[r].x); sts32(fa1[r], e[r].y); sts32(fa2[r], e[r].z);
        asm volatile("st.shared.u16 [%0], %1;" ::"r"(faz[r]), "h"((unsigned short)e[r].w) : "memory");
      }
      fence_async_smem();
      bar_arrive(4, 224);
      __syncwarp();
      if (lane == 0) mbar_arrive(bar + 8 * B_BKV);
      const uint32_t epoch = lds32(sb + SM_EPOCH);
      if (warp < 10) {
        const int m = warp - 8;
        const uint32_t* flag = (const uint32_t*)(scr->flag + (ti * 2 + m) * 8) + lane;
        uint32_t og = __shfl_sync(0xffffffffu, (epoch & 1) * (uint32_t)sizeof(scr->o[0]) + ((ti * 2 + m) * 8 + (tj == 0)) * 9216, 0);
        uint32_t od = __shfl_sync(0xffffffffu, sb + SM_O + m * 65536 + (tj == 0 ? 1024 : 0), 0);
        uint32_t ob = __shfl_sync(0xffffffffu, bar + 8 * (B_OF + m * 7), 0);
        const int slow = __shfl_sync(0xffffffffu, (epoch == 0) * 2 + m, 0);
        if (elect_one()) {
#pragma unroll
          for (int r = 0; r < 7; r++) mbar_expect_tx(bar + 8 * (B_OF + m * 7 + r), 9216);
        }
        __syncwarp();
        mbar_wait(bar + 8 * B_QD);
        mbar_wait(bar + 8 * (B_OS + m));
        spin(POLLGATE);
        while (__any_sync(0xffffffffu, ld_relaxed1(flag) == POISON)) {}
        if (__builtin_expect(slow, 0)) {
          if (slow & 2) { asm volatile("fence.acq_rel.gpu;" ::: "memory"); __syncwarp(); asm volatile("fence.proxy.async;" ::: "memory"); }
          if (slow & 1) mbar_wait(bar + 8 * B_OI);
        }
        const unsigned t_o = clk() - 50;
#pragma unroll 1
        for (int r = 1; r < 8; r++) {
          if (elect_one()) bulk_load(od, (const char*)scr + og, 9216, ob);
          og += r == tj ? 18432 : 9216; od += r == tj ? 10240 : 9216; ob += 8;
          wait_until(t_o, r * OPACE);
          __syncwarp();
        }
        if (lane == 0 && m == 0) mbar_arrive(bar + 8 * B_OI);
      }
    } else {
      bar_sync(0, NTHREADS);
#pragma unroll
      for (int c = 1; c < 9; c++) {
        if (c >= 4) mbar_wait_bounded(bar + 8 * (B_E + c - 4), t_start);
        wait_until(t_start, t_issue(c));
        __syncwarp();
        if (elect_one()) {
          LOAD_X(c); LOAD_W(c);
          if (c < NF) LOAD_Q(c);
          if (c < 8) LOAD_R(c + 1);
          if (c == 8) asm volatile("cp.async.bulk.prefetch.L2.global [%0], 5184;" ::"l"((const char*)wo + b * 5184) : "memory");
        }
      }
      mbar_wait_bounded(bar + 8 * (B_E + 5), t_start);
      wait_until(t_start, t_issue(9) - 128);
      __syncwarp();
      if (elect_one()) {
#pragma unroll
        for (int i = 0; i < 5; i++) {
          if (i < 4) LOAD_QR(i + 1);
          LOAD_Q(q_order(i));
        }
        mbar_expect_tx(bar + 8 * B_WO, 9 * 8192);
        mbar_expect_tx(bar + 8 * B_RW, 10240);
#pragma unroll
        for (int c = 0; c < 5; c++) tma3d(sb + SM_WR + c * 2048, &maps.wor, 512 + tj * 8, c * 8, 0, bar + 8 * B_RW);
      }
      mbar_wait_bounded(bar + 8 * B_VD, t_start);
      __syncwarp();
      if (elect_one()) {
#pragma unroll
        for (int i = 5; i < 9 - NF; i++) LOAD_Q(q_order(i));
#pragma unroll
        for (int c = 0; c < 9; c++) if (c >> 1 != (QS & 3)) tma2d(sb + SM_X + c * 8192, &maps.wo, tj * 64, c * 64, bar + 8 * B_WO);
      }
      __syncwarp();
      mbar_wait_bounded(bar + 8 * B_XS, t_start);
      mbar_wait_bounded(bar + 8 * B_H1, t_start);
      if (elect_one()) {
#pragma unroll
        for (int c = 2 * (QS & 3); c < 2 * (QS & 3) + 2; c++) tma2d(sb + SM_X + c * 8192, &maps.wo, tj * 64, c * 64, bar + 8 * B_WO);
      }
      __syncwarp();
      mbar_wait_bounded(bar + 8 * B_RW, t_start);
      mbar_wait_bounded(bar + 8 * B_BKV, t_start);
#pragma unroll 1
      for (int job = 0; job < 5; job++) swizzle_job(sb + SM_WR + job * 2048, lane);
      if (lane == 0) mbar_arrive(bar + 8 * B_WO);
      uint32_t po = __shfl_sync(0xffffffffu, ((lds32(sb + SM_EPOCH) & 1) ^ 1) * (uint32_t)sizeof(scr->o[0]) + (ti * 16 + tj) * 9216, 0);
      mbar_wait_bounded(bar + 8 * B_OI, t_start);
      const unsigned t_p = clk();
#pragma unroll 1
      for (int i = 1; i < 10; i++, po += 1024) {
        if (elect_one()) {
          asm volatile("cp.async.bulk.global.shared::cta.bulk_group [%0], [%1], 1024;" ::"l"((char*)scr + po), "r"(sb + SM_PB) : "memory");
          asm volatile("cp.async.bulk.global.shared::cta.bulk_group [%0], [%1], 1024;" ::"l"((char*)scr + po + 8 * 9216), "r"(sb + SM_PB) : "memory");
        }
        wait_until(t_p, i * PPACE);
        __syncwarp();
      }
      asm volatile("cp.async.bulk.commit_group;" ::: "memory");
      asm volatile("cp.async.bulk.wait_group.read 0;" ::: "memory");
      __syncwarp();
      mbar_wait_bounded(bar + 8 * B_DONE, t_start);
    }
  }
}

typedef CUresult (*EncodeFn)(CUtensorMap*, CUtensorMapDataType, cuuint32_t, void*, const cuuint64_t*, const cuuint64_t*,
                             const cuuint32_t*, const cuuint32_t*, CUtensorMapInterleave, CUtensorMapSwizzle,
                             CUtensorMapL2promotion, CUtensorMapFloatOOBfill);

void make_map(EncodeFn enc, CUtensorMap* m, const void* ptr, int rank, const cuuint64_t* dims, const cuuint64_t* strides, const cuuint32_t* box,
              CUtensorMapSwizzle sw = CU_TENSOR_MAP_SWIZZLE_128B) {
  const cuuint32_t es[4] = {1, 1, 1, 1};
  enc(m, CU_TENSOR_MAP_DATA_TYPE_BFLOAT16, rank, (void*)ptr, dims, strides, box, es, CU_TENSOR_MAP_INTERLEAVE_NONE,
      sw, CU_TENSOR_MAP_L2_PROMOTION_L2_128B, CU_TENSOR_MAP_FLOAT_OOB_FILL_NONE);
}

}

extern "C" void kernel_launch(void* const* d_in, const int* in_sizes, int n_in, void* d_out, int out_size) {
  const __nv_bfloat16* x = (const __nv_bfloat16*)d_in[0];
  const __nv_bfloat16* wqkv = (const __nv_bfloat16*)d_in[1];
  const __nv_bfloat16* wo = (const __nv_bfloat16*)d_in[2];
  __nv_bfloat16* out = (__nv_bfloat16*)d_out;
  void* fn = nullptr;
  cudaDriverEntryPointQueryResult qr;
  cudaGetDriverEntryPoint("cuTensorMapEncodeTiled", &fn, cudaEnableDefault, &qr);
  EncodeFn enc = (EncodeFn)fn;
  Maps maps;
  { const cuuint64_t d[2] = {576, 2048}, s[1] = {1152}; const cuuint32_t bx[2] = {64, 128}; make_map(enc, &maps.x, x, 2, d, s, bx); }
  { const cuuint64_t d[3] = {576, 576, 3}, s[2] = {3456, 1152}; const cuuint32_t bx[3] = {64, 32, 2}; make_map(enc, &maps.wkv, wqkv, 3, d, s, bx); }
  { const cuuint64_t d[4] = {576, 3, 36, 16}, s[3] = {1152, 16 * 3456, 3456};
    const cuuint32_t bx[4] = {8, 2, 4, 16}, bq[4] = {8, 1, 8, 16};
    make_map(enc, &maps.wr, wqkv, 4, d, s, bx, CU_TENSOR_MAP_SWIZZLE_NONE); make_map(enc, &maps.wqr, wqkv, 4, d, s, bq, CU_TENSOR_MAP_SWIZZLE_NONE); }
  { const cuuint64_t d[2] = {1728, 576}, s[1] = {3456}; const cuuint32_t bx[2] = {64, 64}; make_map(enc, &maps.wq, wqkv, 2, d, s, bx); }
  { const cuuint64_t d[2] = {576, 576}, s[1] = {1152}; const cuuint32_t bx[2] = {64, 64}; make_map(enc, &maps.wo, wo, 2, d, s, bx); }
  { const cuuint64_t d[3] = {576, 36, 16}, s[2] = {16 * 1152, 1152}; const cuuint32_t bx[3] = {8, 8, 16}; make_map(enc, &maps.wor, wo, 3, d, s, bx, CU_TENSOR_MAP_SWIZZLE_NONE); }
  { const cuuint64_t d[2] = {576, 2048}, s[1] = {1152}; const cuuint32_t bx[2] = {64, 16}, br[2] = {8, 16};
    make_map(enc, &maps.out, out, 2, d, s, bx); make_map(enc, &maps.outr, out, 2, d, s, br, CU_TENSOR_MAP_SWIZZLE_NONE); }
  cudaFuncSetAttribute(linattn_kernel, cudaFuncAttributeMaxDynamicSharedMemorySize, SM_TOTAL);
  void* scr = nullptr;
  cudaGetSymbolAddress(&scr, g_scratch);
  Counts counts = {};
  for (int i = 0; i < B_NUM; i++) counts.w[i >> 3] |= bar_count(i) << (4 * (i & 7));
  linattn_kernel<<<NCTA, NTHREADS, SM_TOTAL>>>(wo, (Scratch*)scr, counts, maps);
}
```
